```python
import torch

def _softmax(x, axis=-1):
    return torch.softmax(x, dim=axis)
def _gelu(x):
    return torch.nn.functional.gelu(x, approximate="tanh")
def _silu(x):
    return torch.nn.functional.silu(x)
def _sigmoid(x):
    return torch.sigmoid(x)
def _layernorm(x, axis=-1, eps=1e-5):
    m = x.mean(dim=axis, keepdim=True)
    v = x.var(dim=axis, keepdim=True, unbiased=False)
    return (x - m) / torch.sqrt(v + eps)
def _scatter_add(tgt, idx, src, axis=0):
    return tgt.clone().index_add_(axis, idx, src)
def _segment_sum(src, seg, n):
    out = torch.zeros((n,) + src.shape[1:], dtype=src.dtype)
    return out.index_add_(0, seg, src)
def _pad(x, pw):
    flat = tuple(v for pair in reversed(pw) for v in pair)
    return torch.nn.functional.pad(x, flat)

kernel_name = 'gated_mix__sliding_block__dense_activation_silu__prompt'

def setup_inputs():

    _w = (lambda a: (lambda t: t.to(torch.bfloat16) if t.is_floating_point() else t)(torch.as_tensor(a)))
    def _A_setup():
        B, S, D = 1, 2048, 512
        return {
            "x": _w((lambda *s: torch.randn(*s, dtype=torch.bfloat16) * 0.1)(B, S, D)),
            "wqkv": _w((lambda *s: torch.randn(*s, dtype=torch.bfloat16) * 0.4)(D, 3 * D)),
            "wo": _w((lambda *s: torch.randn(*s, dtype=torch.bfloat16) * 0.1)(D, D)),
        }
    _A_in = _A_setup()

    def _B_setup():
        B, S, D, F = 1, 2048, 512, 1792
        return {
            "x": _w((lambda *s: torch.randn(*s, dtype=torch.bfloat16) * 0.1)(B, S, D)),
            "w1": _w((lambda *s: torch.randn(*s, dtype=torch.bfloat16) * 3.2)(D, F) * (D ** -0.5)),
            "w2": _w((lambda *s: torch.randn(*s, dtype=torch.bfloat16) * 3.2)(F, D) * (F ** -0.5)),
        }
    _B_in = _B_setup()

    return {
        "A_x": _A_in["x"],
        "A_wqkv": _A_in["wqkv"],
        "A_wo": _A_in["wo"],
        "B_x": _B_in["x"],
        "B_w1": _B_in["w1"],
        "B_w2": _B_in["w2"],
        "gate_w": _w((lambda *s: torch.randn(*s, dtype=torch.bfloat16) * 0.1)(512) * 16.0),
    }

def reference(A_x, A_wqkv, A_wo, B_x, B_w1, B_w2, gate_w):
    def _A_ref(x, wqkv, wo):
        B, S, D = x.shape
        H = 32; Dh = D // H; W = 256
        qkv = (lambda x, *d: x.permute(*d))((x @ wqkv).reshape(B, S, 3, H, Dh), 2, 0, 3, 1, 4)
        q, k, v = qkv[0], qkv[1], qkv[2]
        scores = torch.einsum("bhqd,bhkd->bhqk", q, k) * (Dh ** -0.5)
        idx = torch.arange(S)
        mask = (idx[:, None] - idx[None, :] >= 0) & (idx[:, None] - idx[None, :] < W)
        scores = torch.where(mask[None, None], scores, -1e9)
        p = _softmax(scores, axis=-1)
        o = torch.einsum("bhqk,bhkd->bhqd", p, v)
        return (lambda x, *d: x.permute(*d))(o, 0, 2, 1, 3).reshape(B, S, D) @ wo

    def _B_ref(x, w1, w2):
        h = torch.einsum("bsd,df->bsf", x, w1)
        h = _silu(h)
        out = torch.einsum("bsf,fd->bsd", h, w2)
        return out

    x = A_x
    g = _sigmoid((x * gate_w).sum(-1, keepdims=True))
    a = _A_ref(x, A_wqkv, A_wo)
    b = _B_ref(x, B_w1, B_w2)
    return g * a + (1 - g) * b
```

```cpp
#include <cuda_runtime.h>
#include <cuda_bf16.h>
#include <cuda.h>
#include <stdint.h>

namespace gm {

constexpr int NTHREADS = 640;

constexpr uint32_t SM_X    = 0;
constexpr uint32_t SM_R    = 131072;
constexpr uint32_t SM_KV   = SM_R + 49152;
constexpr uint32_t SM_ONES = SM_R + 98304;
constexpr uint32_t SM_G    = SM_ONES + 512;
constexpr uint32_t SM_BAR  = SM_G + 512;
constexpr uint32_t SM_TOTAL = SM_BAR + 1024;

enum : uint32_t {
  B_XFULL = 0, B_WQF = 8, B_WQE = 24, B_W1E = 28, B_PBE = 31,
  B_PBF = 35, B_W1F = 39, B_KVF = 42, B_HSE = 44, B_PR = 47,
  B_GATE = 48, B_QKV = 49, B_QB = 50, B_HSF = 51, B_OD = 58, B_PS = 62, B_COUNT = 63
};
constexpr uint32_t SM_EPOCH = SM_BAR + 1000;

__device__ __align__(1024) uint8_t g_KVQ[128 * 49152];
__device__ __align__(1024) uint8_t g_A[128 * 18 * 4096];
__device__ __align__(1024) uint4 g_P[128 * 1024];
__device__ __align__(1024) uint32_t g_flags[128 * 32];
#define TS(id) do { } while (0)

__device__ __forceinline__ int tid_now() { int t; asm volatile("mov.u32 %0, %%tid.x;" : "=r"(t)); return t < 128 ? t + 512 : t - 128; }
__device__ __forceinline__ uint32_t smem_u32(const void* p) { return (uint32_t)__cvta_generic_to_shared(p); }
__device__ __forceinline__ void mbar_init(uint32_t bar, uint32_t cnt) {
  asm volatile("mbarrier.init.shared::cta.b64 [%0], %1;" ::"r"(bar), "r"(cnt) : "memory");
}
__device__ __forceinline__ void mbar_arrive(uint32_t bar) {
  asm volatile("mbarrier.arrive.shared::cta.b64 _, [%0];" ::"r"(bar) : "memory");
}
__device__ __forceinline__ uint32_t mapa(uint32_t addr, uint32_t rank) {
  uint32_t r;
  asm volatile("mapa.shared::cluster.u32 %0, %1, %2;" : "=r"(r) : "r"(addr), "r"(rank));
  return r;
}
__device__ __forceinline__ void mbar_arrive_remote(uint32_t cluster_addr) {
  asm volatile("mbarrier.arrive.relaxed.cluster.shared::cluster.b64 _, [%0];" ::"r"(cluster_addr) : "memory");
}
__device__ __forceinline__ uint32_t mbar_try(uint32_t bar, uint32_t parity) {
  uint32_t ok;
  asm volatile("{\n.reg .pred p;\nmbarrier.try_wait.parity.shared::cta.b64 p, [%1], %2;\nselp.u32 %0, 1, 0, p;\n}"
               : "=r"(ok) : "r"(bar), "r"(parity) : "memory");
  return ok;
}
constexpr uint32_t SPIN_LIMIT = 1u << 18;
__device__ __forceinline__ void mbar_wait(uint32_t bar, uint32_t parity) {
  uint32_t n = 0;
  while (!mbar_try(bar, parity)) { if (++n > SPIN_LIMIT) break; }
}
__device__ __forceinline__ void mbar_wait_t(uint32_t bar, uint32_t parity) {
  uint32_t n = 0;
  while (!mbar_try(bar, parity)) { if (++n > SPIN_LIMIT) __trap(); }
}
#define ELECT "{\n.reg .pred P;\nelect.sync _|P, 0xffffffff;\n@P "
__device__ __forceinline__ void e_expect(uint32_t bar, uint32_t bytes) {
  asm volatile(ELECT "mbarrier.arrive.expect_tx.shared::cta.b64 _, [%0], %1;\n}" ::"r"(bar), "r"(bytes) : "memory");
}
__device__ __forceinline__ void e_arrive(uint32_t bar) {
  asm volatile(ELECT "mbarrier.arrive.shared::cta.b64 _, [%0];\n}" ::"r"(bar) : "memory");
}
__device__ __forceinline__ void e_tma2d(uint32_t dst, const CUtensorMap* tm, uint32_t bar, int c0, int c1) {
  asm volatile(ELECT "cp.async.bulk.tensor.2d.shared::cluster.global.mbarrier::complete_tx::bytes [%0], [%1, {%3, %4}], [%2];\n}"
               ::"r"(dst), "l"((uint64_t)tm), "r"(bar), "r"(c0), "r"(c1) : "memory");
}
__device__ __forceinline__ void e_tma2d_mc(uint32_t dst, const CUtensorMap* tm, uint32_t bar, int c0, int c1) {
  asm volatile(ELECT "cp.async.bulk.tensor.2d.shared::cluster.global.mbarrier::complete_tx::bytes.multicast::cluster [%0], [%1, {%3, %4}], [%2], %5;\n}"
               ::"r"(dst), "l"((uint64_t)tm), "r"(bar), "r"(c0), "r"(c1), "h"((uint16_t)3) : "memory");
}
__device__ __forceinline__ void e_s2g(void* dst, uint32_t src, uint32_t bytes) {
  asm volatile(ELECT "cp.async.bulk.global.shared::cta.bulk_group [%0], [%1], %2;\n}" ::"l"(dst), "r"(src), "r"(bytes) : "memory");
}
__device__ __forceinline__ void e_g2s(uint32_t dst, const void* src, uint32_t bytes, uint32_t bar) {
  asm volatile(ELECT "cp.async.bulk.shared::cluster.global.mbarrier::complete_tx::bytes [%0], [%1], %2, [%3];\n}"
               ::"r"(dst), "l"(src), "r"(bytes), "r"(bar) : "memory");
}
__device__ __forceinline__ void e_l2_prefetch(const void* src, uint32_t bytes) {
  asm volatile(ELECT "cp.async.bulk.prefetch.L2.global [%0], %1;\n}" ::"l"(src), "r"(bytes) : "memory");
}
__device__ __forceinline__ void e_st_flag(uint32_t* p, uint32_t v) {
  asm volatile(ELECT "st.relaxed.gpu.global.u32 [%0], %1;\n}" ::"l"(p), "r"(v) : "memory");
}
__device__ __forceinline__ void bulk_commit() { asm volatile("cp.async.bulk.commit_group;" ::: "memory"); }
__device__ __forceinline__ void bulk_wait_read() { asm volatile("cp.async.bulk.wait_group.read 0;" ::: "memory"); }
__device__ __forceinline__ void bulk_wait_all() { asm volatile("cp.async.bulk.wait_group 0;" ::: "memory"); }
__device__ __forceinline__ void stmatrix4(uint32_t addr, uint32_t r0, uint32_t r1, uint32_t r2, uint32_t r3) {
  asm volatile("stmatrix.sync.aligned.m8n8.x4.shared.b16 [%0], {%1, %2, %3, %4};" ::"r"(addr), "r"(r0), "r"(r1), "r"(r2), "r"(r3) : "memory");
}
__device__ __forceinline__ void fence_async_smem() { asm volatile("fence.proxy.async.shared::cta;" ::: "memory"); }
__device__ __forceinline__ void prefetch_tmap(const CUtensorMap* tm) {
  asm volatile("prefetch.tensormap [%0];" ::"l"((uint64_t)tm) : "memory");
}
__device__ __forceinline__ uint32_t ld_flag(const uint32_t* p) {
  uint32_t v;
  asm volatile("ld.relaxed.gpu.global.u32 %0, [%1];" : "=r"(v) : "l"(p) : "memory");
  return v;
}
__device__ __forceinline__ void wait_flag(const uint32_t* p, uint32_t epoch) {
  uint32_t n = 0;
  while ((int32_t)(ld_flag(p) - epoch) < 0) { __nanosleep(32); if (++n > 8 * SPIN_LIMIT) __trap(); }
}
__device__ __forceinline__ uint4 ld_q(const uint4* p) {
  uint4 v;
  asm volatile("ld.relaxed.cta.global.v4.u32 {%0, %1, %2, %3}, [%4];" : "=r"(v.x), "=r"(v.y), "=r"(v.z), "=r"(v.w) : "l"(p) : "memory");
  return v;
}
__device__ __forceinline__ uint32_t pack_bf16(float lo, float hi) {
  uint32_t r;
  asm("cvt.rn.bf16x2.f32 %0, %1, %2;" : "=r"(r) : "f"(hi), "f"(lo));
  return r;
}
__device__ __forceinline__ float ex2(float x) { float y; asm("ex2.approx.ftz.f32 %0, %1;" : "=f"(y) : "f"(x)); return y; }
__device__ __forceinline__ float rcp(float x) { float y; asm("rcp.approx.ftz.f32 %0, %1;" : "=f"(y) : "f"(x)); return y; }
#define WG_FENCE() asm volatile("wgmma.fence.sync.aligned;" ::: "memory")
#define WG_COMMIT() asm volatile("wgmma.commit_group.sync.aligned;" ::: "memory")
#define WG_WAIT(n) asm volatile("wgmma.wait_group.sync.aligned %0;" ::"n"(n) : "memory")
template <int N> __device__ __forceinline__ void reg_fence(float (&a)[N]) {
#pragma unroll
  for (int i = 0; i < N; i++) asm volatile("" : "+f"(a[i])::"memory");
}
constexpr uint32_t HI128 = (1024u >> 4) | (1u << 30), HI64 = (512u >> 4) | (2u << 30), HI32 = (256u >> 4) | (3u << 30);
__device__ __forceinline__ uint64_t dsc(uint32_t lo, uint32_t hi) { return ((uint64_t)hi << 32) | lo; }
__device__ __forceinline__ int cta_of(int rb, int j) { return (((rb >> 1) * 8 + j) << 1) | (rb & 1); }

__device__ __forceinline__ void wgmma_ss_n128(float (&d)[64], uint64_t da, uint64_t db, int sd) {
  asm volatile("{\n.reg .pred p;\nsetp.ne.b32 p, %66, 0;\n"
    "wgmma.mma_async.sync.aligned.m64n128k16.f32.bf16.bf16 {%0, %1, %2, %3, %4, %5, %6, %7, %8, %9, %10, %11, %12, %13, %14, %15, %16, %17, %18, %19, %20, %21, %22, %23, %24, %25, %26, %27, %28, %29, %30, %31, %32, %33, %34, %35, %36, %37, %38, %39, %40, %41, %42, %43, %44, %45, %46, %47, %48, %49, %50, %51, %52, %53, %54, %55, %56, %57, %58, %59, %60, %61, %62, %63}, %64, %65, p, 1, 1, 0, 1;\n}\n"
    : "+f"(d[0]), "+f"(d[1]), "+f"(d[2]), "+f"(d[3]), "+f"(d[4]), "+f"(d[5]), "+f"(d[6]), "+f"(d[7]), "+f"(d[8]), "+f"(d[9]), "+f"(d[10]), "+f"(d[11]), "+f"(d[12]), "+f"(d[13]), "+f"(d[14]), "+f"(d[15]), "+f"(d[16]), "+f"(d[17]), "+f"(d[18]), "+f"(d[19]), "+f"(d[20]), "+f"(d[21]), "+f"(d[22]), "+f"(d[23]), "+f"(d[24]), "+f"(d[25]), "+f"(d[26]), "+f"(d[27]), "+f"(d[28]), "+f"(d[29]), "+f"(d[30]), "+f"(d[31]), "+f"(d[32]), "+f"(d[33]), "+f"(d[34]), "+f"(d[35]), "+f"(d[36]), "+f"(d[37]), "+f"(d[38]), "+f"(d[39]), "+f"(d[40]), "+f"(d[41]), "+f"(d[42]), "+f"(d[43]), "+f"(d[44]), "+f"(d[45]), "+f"(d[46]), "+f"(d[47]), "+f"(d[48]), "+f"(d[49]), "+f"(d[50]), "+f"(d[51]), "+f"(d[52]), "+f"(d[53]), "+f"(d[54]), "+f"(d[55]), "+f"(d[56]), "+f"(d[57]), "+f"(d[58]), "+f"(d[59]), "+f"(d[60]), "+f"(d[61]), "+f"(d[62]), "+f"(d[63])
    : "l"(da), "l"(db), "r"(sd));
}
__device__ __forceinline__ void wgmma_ss_n96(float (&d)[48], uint64_t da, uint64_t db, int sd) {
  asm volatile("{\n.reg .pred p;\nsetp.ne.b32 p, %50, 0;\n"
    "wgmma.mma_async.sync.aligned.m64n96k16.f32.bf16.bf16 {%0, %1, %2, %3, %4, %5, %6, %7, %8, %9, %10, %11, %12, %13, %14, %15, %16, %17, %18, %19, %20, %21, %22, %23, %24, %25, %26, %27, %28, %29, %30, %31, %32, %33, %34, %35, %36, %37, %38, %39, %40, %41, %42, %43, %44, %45, %46, %47}, %48, %49, p, 1, 1, 0, 1;\n}\n"
    : "+f"(d[0]), "+f"(d[1]), "+f"(d[2]), "+f"(d[3]), "+f"(d[4]), "+f"(d[5]), "+f"(d[6]), "+f"(d[7]), "+f"(d[8]), "+f"(d[9]), "+f"(d[10]), "+f"(d[11]), "+f"(d[12]), "+f"(d[13]), "+f"(d[14]), "+f"(d[15]), "+f"(d[16]), "+f"(d[17]), "+f"(d[18]), "+f"(d[19]), "+f"(d[20]), "+f"(d[21]), "+f"(d[22]), "+f"(d[23]), "+f"(d[24]), "+f"(d[25]), "+f"(d[26]), "+f"(d[27]), "+f"(d[28]), "+f"(d[29]), "+f"(d[30]), "+f"(d[31]), "+f"(d[32]), "+f"(d[33]), "+f"(d[34]), "+f"(d[35]), "+f"(d[36]), "+f"(d[37]), "+f"(d[38]), "+f"(d[39]), "+f"(d[40]), "+f"(d[41]), "+f"(d[42]), "+f"(d[43]), "+f"(d[44]), "+f"(d[45]), "+f"(d[46]), "+f"(d[47])
    : "l"(da), "l"(db), "r"(sd));
}
__device__ __forceinline__ void wgmma_ss_n64(float (&d)[32], uint64_t da, uint64_t db, int sd) {
  asm volatile("{\n.reg .pred p;\nsetp.ne.b32 p, %34, 0;\n"
    "wgmma.mma_async.sync.aligned.m64n64k16.f32.bf16.bf16 {%0, %1, %2, %3, %4, %5, %6, %7, %8, %9, %10, %11, %12, %13, %14, %15, %16, %17, %18, %19, %20, %21, %22, %23, %24, %25, %26, %27, %28, %29, %30, %31}, %32, %33, p, 1, 1, 0, 1;\n}\n"
    : "+f"(d[0]), "+f"(d[1]), "+f"(d[2]), "+f"(d[3]), "+f"(d[4]), "+f"(d[5]), "+f"(d[6]), "+f"(d[7]), "+f"(d[8]), "+f"(d[9]), "+f"(d[10]), "+f"(d[11]), "+f"(d[12]), "+f"(d[13]), "+f"(d[14]), "+f"(d[15]), "+f"(d[16]), "+f"(d[17]), "+f"(d[18]), "+f"(d[19]), "+f"(d[20]), "+f"(d[21]), "+f"(d[22]), "+f"(d[23]), "+f"(d[24]), "+f"(d[25]), "+f"(d[26]), "+f"(d[27]), "+f"(d[28]), "+f"(d[29]), "+f"(d[30]), "+f"(d[31])
    : "l"(da), "l"(db), "r"(sd));
}
__device__ __forceinline__ void wgmma_rs_n64_set(float (&d)[32], uint32_t a0, uint32_t a1, uint32_t a2, uint32_t a3, uint64_t db) {
  asm volatile("wgmma.mma_async.sync.aligned.m64n64k16.f32.bf16.bf16 {%0, %1, %2, %3, %4, %5, %6, %7, %8, %9, %10, %11, %12, %13, %14, %15, %16, %17, %18, %19, %20, %21, %22, %23, %24, %25, %26, %27, %28, %29, %30, %31}, {%32, %33, %34, %35}, %36, 0, 1, 1, 0;\n"
    : "+f"(d[0]), "+f"(d[1]), "+f"(d[2]), "+f"(d[3]), "+f"(d[4]), "+f"(d[5]), "+f"(d[6]), "+f"(d[7]), "+f"(d[8]), "+f"(d[9]), "+f"(d[10]), "+f"(d[11]), "+f"(d[12]), "+f"(d[13]), "+f"(d[14]), "+f"(d[15]), "+f"(d[16]), "+f"(d[17]), "+f"(d[18]), "+f"(d[19]), "+f"(d[20]), "+f"(d[21]), "+f"(d[22]), "+f"(d[23]), "+f"(d[24]), "+f"(d[25]), "+f"(d[26]), "+f"(d[27]), "+f"(d[28]), "+f"(d[29]), "+f"(d[30]), "+f"(d[31])
    : "r"(a0), "r"(a1), "r"(a2), "r"(a3), "l"(db));
}
__device__ __forceinline__ void wgmma_rs_n24_set(float (&d)[12], uint32_t a0, uint32_t a1, uint32_t a2, uint32_t a3, uint64_t db) {
  asm volatile("wgmma.mma_async.sync.aligned.m64n24k16.f32.bf16.bf16 {%0, %1, %2, %3, %4, %5, %6, %7, %8, %9, %10, %11}, {%12, %13, %14, %15}, %16, 0, 1, 1, 1;\n"
    : "=f"(d[0]), "=f"(d[1]), "=f"(d[2]), "=f"(d[3]), "=f"(d[4]), "=f"(d[5]), "=f"(d[6]), "=f"(d[7]), "=f"(d[8]), "=f"(d[9]), "=f"(d[10]), "=f"(d[11])
    : "r"(a0), "r"(a1), "r"(a2), "r"(a3), "l"(db));
}
__device__ __forceinline__ void wgmma_rs_n32_set(float (&d)[16], uint32_t a0, uint32_t a1, uint32_t a2, uint32_t a3, uint64_t db) {
  asm volatile("wgmma.mma_async.sync.aligned.m64n32k16.f32.bf16.bf16 {%0, %1, %2, %3, %4, %5, %6, %7, %8, %9, %10, %11, %12, %13, %14, %15}, {%16, %17, %18, %19}, %20, 0, 1, 1, 0;\n"
    : "+f"(d[0]), "+f"(d[1]), "+f"(d[2]), "+f"(d[3]), "+f"(d[4]), "+f"(d[5]), "+f"(d[6]), "+f"(d[7]), "+f"(d[8]), "+f"(d[9]), "+f"(d[10]), "+f"(d[11]), "+f"(d[12]), "+f"(d[13]), "+f"(d[14]), "+f"(d[15])
    : "r"(a0), "r"(a1), "r"(a2), "r"(a3), "l"(db));
}
__device__ __forceinline__ void wgmma_rs_n24_mnmaj(float (&d)[12], uint32_t a0, uint32_t a1, uint32_t a2, uint32_t a3, uint64_t db, int sd) {
  asm volatile("{\n.reg .pred p;\nsetp.ne.b32 p, %17, 0;\n"
    "wgmma.mma_async.sync.aligned.m64n24k16.f32.bf16.bf16 {%0, %1, %2, %3, %4, %5, %6, %7, %8, %9, %10, %11}, {%12, %13, %14, %15}, %16, p, 1, 1, 1;\n}\n"
    : "+f"(d[0]), "+f"(d[1]), "+f"(d[2]), "+f"(d[3]), "+f"(d[4]), "+f"(d[5]), "+f"(d[6]), "+f"(d[7]), "+f"(d[8]), "+f"(d[9]), "+f"(d[10]), "+f"(d[11])
    : "r"(a0), "r"(a1), "r"(a2), "r"(a3), "l"(db), "r"(sd));
}

constexpr float LOG2E = 1.4426950408889634f;
constexpr float SCALE_C = 0.25f * LOG2E;

__device__ __forceinline__ uint32_t silu2(uint32_t v2, uint32_t s2) {
  uint32_t h2, t2, hv, r;
  asm("mul.rn.bf16x2 %0, %1, %2;" : "=r"(h2) : "r"(v2), "r"(0x3F003F00u));
  asm("tanh.approx.bf16x2 %0, %1;" : "=r"(t2) : "r"(h2));
  asm("mul.rn.bf16x2 %0, %1, %2;" : "=r"(hv) : "r"(v2), "r"(s2));
  asm("fma.rn.bf16x2 %0, %1, %2, %1;" : "=r"(r) : "r"(hv), "r"(t2));
  return r;
}

__device__ __forceinline__ void att_s(float (&X)[32], const uint4& qf, uint32_t klo) {
  wgmma_rs_n64_set(X, qf.x, qf.y, qf.z, qf.w, dsc(klo, HI32));
}
__device__ __forceinline__ void att_pv16(float (&O)[12], const uint32_t (&P)[16], uint32_t vlo, bool first) {
#pragma unroll
  for (int jj = 0; jj < 4; jj++) {
    const uint64_t d = dsc(vlo + jj * 32 - ((uint32_t)(jj * 32) << 16), HI32);
    if (jj == 0 && first) wgmma_rs_n24_set(O, P[4 * jj], P[4 * jj + 1], P[4 * jj + 2], P[4 * jj + 3], d);
    else wgmma_rs_n24_mnmaj(O, P[4 * jj], P[4 * jj + 1], P[4 * jj + 2], P[4 * jj + 3], d, 1);
  }
}
__device__ __forceinline__ void att_exp16(const float (&X)[32], uint32_t (&P)[16], float mc0, float mc1) {
#pragma unroll
  for (int i = 0; i < 16; i++) {
    const float mc = (i & 1) ? mc1 : mc0;
    P[i] = pack_bf16(ex2(X[2 * i] - mc), ex2(X[2 * i + 1] - mc));
  }
}
template <int N> __device__ __forceinline__ void reg_fence_u(uint32_t (&a)[N]) {
#pragma unroll
  for (int i = 0; i < N; i++) asm volatile("" : "+r"(a[i])::"memory");
}

#define FORCE_FALLBACK 0
__device__ __forceinline__ void att_fallback(const uint8_t* kv, const uint4& qf, int a, int w4, int kb_min, int lane, float (&O)[12]) {
#pragma unroll 1
  for (int r = 0; r < 16; r++) {
    const uint32_t lo = (r < 8) ? qf.x : qf.y, hi = (r < 8) ? qf.z : qf.w;
    float qv[16];
#pragma unroll
    for (int t = 0; t < 4; t++) {
      const uint32_t l = __shfl_sync(0xffffffffu, lo, 4 * (r & 7) + t), h = __shfl_sync(0xffffffffu, hi, 4 * (r & 7) + t);
      qv[2 * t] = __uint_as_float(l << 16); qv[2 * t + 1] = __uint_as_float(l & 0xffff0000u);
      qv[8 + 2 * t] = __uint_as_float(h << 16); qv[9 + 2 * t] = __uint_as_float(h & 0xffff0000u);
    }
    const int qpos = (a + 4) * 64 + w4 * 16 + r;
    float m = -INFINITY;
#pragma unroll 1
    for (int pass = 0; pass < 2; pass++) {
      float l = 0.f, o[16];
#pragma unroll
      for (int d = 0; d < 16; d++) o[d] = 0.f;
#pragma unroll 1
      for (int t = 0; t < 8; t++) {
        const int key = qpos - 255 + t * 32 + lane;
        if (key >= kb_min * 64) {
          const uint32_t sw = ((key >> 2) & 1) * 16;
          const uint32_t ko = (key >> 7) * 8192 + (key & 127) * 32;
          float s = 0.f;
#pragma unroll
          for (int c = 0; c < 2; c++) {
            const uint4 kk = *reinterpret_cast<const uint4*>(kv + ko + ((c * 16) ^ sw));
            const uint32_t w[4] = {kk.x, kk.y, kk.z, kk.w};
#pragma unroll
            for (int e = 0; e < 4; e++) {
              s = fmaf(qv[8 * c + 2 * e], __uint_as_float(w[e] << 16), s);
              s = fmaf(qv[8 * c + 2 * e + 1], __uint_as_float(w[e] & 0xffff0000u), s);
            }
          }
          if (pass == 0) {
            m = fmaxf(m, s);
          } else {
            const float p = ex2(s - m);
            l += p;
#pragma unroll
            for (int c = 0; c < 2; c++) {
              const uint4 vv = *reinterpret_cast<const uint4*>(kv + 4096 + ko + ((c * 16) ^ sw));
              const uint32_t w[4] = {vv.x, vv.y, vv.z, vv.w};
#pragma unroll
              for (int e = 0; e < 4; e++) {
                o[8 * c + 2 * e] = fmaf(p, __uint_as_float(w[e] << 16), o[8 * c + 2 * e]);
                o[8 * c + 2 * e + 1] = fmaf(p, __uint_as_float(w[e] & 0xffff0000u), o[8 * c + 2 * e + 1]);
              }
            }
          }
        }
      }
      if (pass == 0) {
#pragma unroll
        for (int x = 16; x >= 1; x >>= 1) m = fmaxf(m, __shfl_xor_sync(0xffffffffu, m, x));
      } else {
#pragma unroll
        for (int x = 16; x >= 1; x >>= 1) l += __shfl_xor_sync(0xffffffffu, l, x);
        const float inv = 1.0f / l;
#pragma unroll
        for (int d = 0; d < 16; d++) {
#pragma unroll
          for (int x = 16; x >= 1; x >>= 1) o[d] += __shfl_xor_sync(0xffffffffu, o[d], x);
        }
        if ((lane >> 2) == (r & 7)) {
          const int q = lane & 3;
          float v0 = 0.f, v1 = 0.f, v2 = 0.f, v3 = 0.f;
#pragma unroll
          for (int t = 0; t < 4; t++)
            if (q == t) { v0 = o[2 * t]; v1 = o[2 * t + 1]; v2 = o[8 + 2 * t]; v3 = o[9 + 2 * t]; }
          if (r < 8) { O[0] = v0 * inv; O[1] = v1 * inv; O[4] = v2 * inv; O[5] = v3 * inv; }
          else       { O[2] = v0 * inv; O[3] = v1 * inv; O[6] = v2 * inv; O[7] = v3 * inv; }
        }
      }
    }
  }
}

template <int HF>
__device__ __forceinline__ void att_merged_half(float (&A)[16], const float (&B)[16], uint32_t (&P)[16], int Dq, int Dsel, uint32_t fmask,
                                                float& mc0, float& mc1) {
#pragma unroll
  for (int nb = 0; nb < 4; nb++)
#pragma unroll
    for (int h = 0; h < 2; h++)
#pragma unroll
      for (int e = 0; e < 2; e++) {
        const bool vl = (8 * (4 * HF + nb - h) + e) <= Dsel;
        A[4 * nb + 2 * h + e] = vl ? A[4 * nb + 2 * h + e] : B[4 * nb + 2 * h + e];
      }
  if (HF == 0) {
    float t0 = fmaxf(fmaxf(A[0], A[1]), fmaxf(A[4], A[5])), t1 = fmaxf(fmaxf(A[2], A[3]), fmaxf(A[6], A[7]));
    t0 = fmaxf(t0, fmaxf(fmaxf(A[8], A[9]), fmaxf(A[12], A[13]))); t1 = fmaxf(t1, fmaxf(fmaxf(A[10], A[11]), fmaxf(A[14], A[15])));
    t0 = fmaxf(t0, __shfl_xor_sync(0xffffffffu, t0, 1)); t1 = fmaxf(t1, __shfl_xor_sync(0xffffffffu, t1, 1));
    t0 = fmaxf(t0, __shfl_xor_sync(0xffffffffu, t0, 2)); t1 = fmaxf(t1, __shfl_xor_sync(0xffffffffu, t1, 2));
    mc0 = t0; mc1 = t1;
  }
  const int e16 = 16 * (Dq + 1);
#pragma unroll
  for (int i = 0; i < 8; i++) {
    const int nb = i >> 1, h = i & 1;
    const float mc = h ? mc1 : mc0;
    const uint32_t p = pack_bf16(ex2(A[2 * i] - mc), ex2(A[2 * i + 1] - mc));
    uint32_t m;
    asm("bmsk.clamp.b32 %0, %1, %2;" : "=r"(m) : "r"(0), "r"(max(e16 - 128 * (4 * HF + nb - h), 0)));
    P[i] = p & m;
    P[8 + i] = p & ~m & fmask;
  }
}
__device__ __forceinline__ uint64_t vdsc(uint32_t vlo, uint32_t off16) { return dsc(vlo + off16 - (off16 << 16), HI32); }
__device__ __forceinline__ bool att_norm(float (&O)[12]) {
  const float i0 = rcp(O[8]), i1 = rcp(O[10]);
  O[0] *= i0; O[1] *= i0; O[4] *= i0; O[5] *= i0;
  O[2] *= i1; O[3] *= i1; O[6] *= i1; O[7] *= i1;
  const float sa = ((fabsf(O[0]) + fabsf(O[1])) + (fabsf(O[2]) + fabsf(O[3]))) + ((fabsf(O[4]) + fabsf(O[5])) + (fabsf(O[6]) + fabsf(O[7])));
  return (fmaxf(O[8], O[10]) < 1.2676506e30f) && (fminf(O[8], O[10]) > 7.8886e-31f) && (O[8] == O[8]) && (O[10] == O[10]) && (sa < 3.0e38f);
}

__global__ void __cluster_dims__(2, 1, 1) __launch_bounds__(NTHREADS, 1)
fused_kernel(const __grid_constant__ CUtensorMap tm_x, const __grid_constant__ CUtensorMap tm_wqkv,
             const __grid_constant__ CUtensorMap tm_w1, const __grid_constant__ CUtensorMap tm_w2,
             const __grid_constant__ CUtensorMap tm_w2h,
             const __grid_constant__ CUtensorMap tm_wo, __nv_bfloat16* __restrict__ out,
             const __nv_bfloat16* __restrict__ gate_w,
             const uint8_t* __restrict__ w1_raw, const uint8_t* __restrict__ w2_raw, const uint8_t* __restrict__ wo_raw) {
  extern __shared__ __align__(1024) uint8_t smem[];
  const uint32_t sb = smem_u32(smem);
  const int pwarp = __shfl_sync(0xffffffffu, threadIdx.x >> 5, 0);
  const int warp = pwarp < 4 ? pwarp + 16 : pwarp - 4;
  const int b = blockIdx.x, cr = b & 1, j = (b >> 1) & 7, rb = ((b >> 4) << 1) | cr;
  const int jk = j & 1, jn = j >> 1;
  auto BAR = [&](uint32_t i) { return sb + SM_BAR + i * 8; };

  if (threadIdx.x == 0) TS(0);
  if ((threadIdx.x & 31) == 0) {
#pragma unroll
    for (uint32_t r = 0; r < 4; r++) {
      const uint32_t i = 8 + warp + 20 * r;
      if (i < B_COUNT && warp != 16 && i != B_WQF) {
        const uint32_t cnt = (i >= B_GATE) ? 8 : ((i >= B_WQE && i < B_PBF) ? 16 : 1);
        mbar_init(BAR(i), cnt);
      }
    }
    asm volatile("fence.mbarrier_init.release.cluster;" ::: "memory");
  }
  if (warp == 16) {
    if ((threadIdx.x & 31) == 0) { mbar_init(BAR(B_XFULL), 1); mbar_init(BAR(B_WQF), 1); mbar_init(BAR(B_XFULL + 1), 1); }
    fence_async_smem();
    __syncwarp();
    e_expect(BAR(B_XFULL), 16384);
    e_tma2d(sb + SM_X, &tm_x, BAR(B_XFULL), 0, rb * 128);
    e_expect(BAR(B_WQF), 12288);
#pragma unroll 1
    for (int t = 0; t < 3; t++) e_tma2d(sb + SM_R + t * 4096, &tm_wqkv, BAR(B_WQF), ((t + 1) % 3) * 512 + j * 64, 0);
    e_expect(BAR(B_XFULL + 1), 16384);
    e_tma2d(sb + SM_X + 16384, &tm_x, BAR(B_XFULL + 1), 64, rb * 128);
    if ((threadIdx.x & 31) == 0) {
#pragma unroll
      for (uint32_t r = 0; r < 4; r++) {
        const uint32_t i = 8 + 16 + 20 * r;
        if (i < B_COUNT) mbar_init(BAR(i), (i >= B_GATE) ? 8 : ((i >= B_WQE && i < B_PBF) ? 16 : 1));
      }
#pragma unroll 1
      for (int c = 2; c < 8; c++) mbar_init(BAR(B_XFULL + c), 1);
      asm volatile("fence.mbarrier_init.release.cluster;" ::: "memory");
    }
  }
  fence_async_smem();
  __syncthreads();
  asm volatile("barrier.cluster.arrive.relaxed.aligned;" ::: "memory");
  if (threadIdx.x == 128) TS(7);

  if (warp < 8) {
    asm volatile("setmaxnreg.inc.sync.aligned.u32 128;");
    const int tid = tid_now(), lane = tid & 31;
    const uint32_t r16 = lane & 15, hf16 = lane >> 4;
    const uint32_t pan_off = r16 * 32 + ((hf16 ^ ((r16 >> 2) & 1)) * 16);
    const int wg = warp >> 2;
    const int row0 = warp * 16 + (lane >> 2);
    const uint32_t sbl = sb & 0x3FFFFu;
    const uint32_t xlo = ((sbl + SM_X + wg * 8192) >> 4) | (1u << 16);
    const uint32_t rlo = ((sbl + SM_R) >> 4) | ((8192u >> 4) << 16);
    asm volatile("barrier.cluster.wait.aligned;" ::: "memory");
    const uint32_t relb = mapa(sb + SM_BAR, cr ^ (lane & 1 ? 1 : 0));
    auto release = [&](uint32_t i) { if (lane < 2) mbar_arrive_remote(relb + i * 8); };
    const uint32_t qlo = ((sbl + SM_R) >> 4) | ((4096u >> 4) << 16);
#pragma unroll 1
    for (int p = 0; p < 2; p++) {
      float aq[48];
#pragma unroll 1
      for (int c = 0; c < 8; c++) {
        if (p == 0) mbar_wait(BAR(B_XFULL + c), 0);
        mbar_wait(BAR(B_WQF + 8 * p + c), 0);
        if (tid == 0 && p == 0) TS(40 + c);
        const uint32_t al = xlo + c * 1024, bl = qlo + (p == 0 ? c : (c & 3)) * 768;
        WG_FENCE();
#pragma unroll
        for (int kk = 0; kk < 4; kk++) wgmma_ss_n96(aq, dsc(al + kk * 2, HI128), dsc(bl + kk * 64, HI64), (c | kk) != 0);
        WG_COMMIT();
        WG_WAIT(1);
        if (c >= 1 && c <= 4) release(B_WQE + c - 1);
        if (p == 1 && c >= 6) release(B_W1E + c - 6);
      }
      WG_WAIT(0);
      reg_fence(aq);
      if (p == 1) release(B_W1E + 2);
      if (tid == 0) TS(p == 0 ? 18 : 1);
      asm volatile("bar.sync 5, 256;" ::: "memory");
      const uint32_t kst = sb + SM_KV + warp * 512 + pan_off + (p == 0 ? 16384 : 24576);
      uint4* qdst = reinterpret_cast<uint4*>(g_KVQ + (size_t)b * 49152 + 32768) + p * 512 + tid;
#pragma unroll
      for (int hl = 0; hl < 2; hl++) {
        const uint32_t d = kst + hl * (p == 0 ? 24576 : 8192);
        stmatrix4(d, pack_bf16(aq[8 * hl], aq[8 * hl + 1]), pack_bf16(aq[8 * hl + 2], aq[8 * hl + 3]),
                  pack_bf16(aq[8 * hl + 4], aq[8 * hl + 5]), pack_bf16(aq[8 * hl + 6], aq[8 * hl + 7]));
        stmatrix4(d + 4096, pack_bf16(aq[16 + 8 * hl], aq[17 + 8 * hl]), pack_bf16(aq[18 + 8 * hl], aq[19 + 8 * hl]),
                  pack_bf16(aq[20 + 8 * hl], aq[21 + 8 * hl]), pack_bf16(aq[22 + 8 * hl], aq[23 + 8 * hl]));
        qdst[hl * 256] =
            make_uint4(pack_bf16(aq[32 + 8 * hl] * SCALE_C, aq[33 + 8 * hl] * SCALE_C), pack_bf16(aq[34 + 8 * hl] * SCALE_C, aq[35 + 8 * hl] * SCALE_C),
                       pack_bf16(aq[36 + 8 * hl] * SCALE_C, aq[37 + 8 * hl] * SCALE_C), pack_bf16(aq[38 + 8 * hl] * SCALE_C, aq[39 + 8 * hl] * SCALE_C));
      }
      fence_async_smem();
      __syncwarp();
      if (lane == 0) mbar_arrive(BAR(B_QKV + p));
      if (tid == 0 && p == 0) TS(6);
    }
    int sl = 0, psl = 0; uint32_t ph = 0;
    float a0[64];
#pragma unroll 1
    for (int n = 0; n < 8; n++) {
      mbar_wait(BAR(B_W1F + sl), ph);
      if (tid == 0) TS(136 + n);
      const uint32_t al = xlo + n * 1024, bl = rlo + sl * 1024;
      WG_FENCE();
      wgmma_ss_n128(a0, dsc(al, HI128), dsc(bl, HI128), n != 0);
      wgmma_ss_n128(a0, dsc(al + 2, HI128), dsc(bl + 128, HI128), 1);
      WG_COMMIT();
      WG_WAIT(1);
      if (n > 0) release(B_W1E + psl);
      wgmma_ss_n128(a0, dsc(al + 4, HI128), dsc(bl + 256, HI128), 1);
      wgmma_ss_n128(a0, dsc(al + 6, HI128), dsc(bl + 384, HI128), 1);
      WG_COMMIT();
      WG_WAIT(0);
      psl = sl;
      if (++sl == 3) { sl = 0; ph ^= 1; }
    }
    WG_WAIT(0);
    reg_fence(a0);
    uint32_t h0[32];
#pragma unroll
    for (int i = 0; i < 32; i++) h0[i] = pack_bf16(a0[2 * i], a0[2 * i + 1]);
    if (tid == 0) TS(2);
    mbar_wait(BAR(B_GATE), 0);
    const float og0 = 0.5f - 0.5f * reinterpret_cast<const float*>(smem + SM_G)[row0];
    const float og1 = 0.5f - 0.5f * reinterpret_cast<const float*>(smem + SM_G)[row0 + 8];
    const uint32_t omg0 = pack_bf16(og0, og0), omg1 = pack_bf16(og1, og1);
    const uint32_t hst = sb + warp * 512 + pan_off;
#define H_PAIR(e, NE, off, fb, hsf)                                                                                         \
    {                                                                                                                       \
      const uint32_t r0 = silu2(e[0], omg0), r1 = silu2(e[1], omg1), r2 = silu2(e[2], omg0), r3 = silu2(e[3], omg1);        \
      const uint32_t r4 = silu2(e[4], omg0), r5 = silu2(e[5], omg1), r6 = silu2(e[6], omg0), r7 = silu2(e[7], omg1);        \
      _Pragma("unroll") for (int i = 0; i < NE - 8; i++) e[i] = e[i + 8];                                                   \
      mbar_wait(BAR(fb), 0);                                                                                                \
      stmatrix4(hst + (off), r0, r1, r2, r3);                                                                               \
      stmatrix4(hst + (off) + 4096, r4, r5, r6, r7);                                                                        \
      fence_async_smem();                                                                                                   \
      __syncwarp();                                                                                                         \
      if (lane == 0) mbar_arrive(BAR(B_HSF + (hsf)));                                                                       \
    }
    float a1[48];
#define P1_STAGE()                                                                              \
      mbar_wait(BAR(B_W1F + sl), ph);                                                           \
      if (tid == 0) TS(144 + n);                                                                \
      {                                                                                         \
        const uint32_t al = xlo + n * 1024, bl = rlo + sl * 1024;                               \
        WG_FENCE();                                                                             \
        wgmma_ss_n96(a1, dsc(al, HI128), dsc(bl, HI128), n != 0);                               \
        wgmma_ss_n96(a1, dsc(al + 2, HI128), dsc(bl + 128, HI128), 1);                          \
        WG_COMMIT();                                                                            \
        WG_WAIT(1);                                                                             \
        release(B_W1E + psl);                                                                   \
        if (n > 0 && !(n & 1)) release(B_PBE + (n >> 1) - 1);                                   \
        wgmma_ss_n96(a1, dsc(al + 4, HI128), dsc(bl + 256, HI128), 1);                          \
        wgmma_ss_n96(a1, dsc(al + 6, HI128), dsc(bl + 384, HI128), 1);                          \
        WG_COMMIT();                                                                            \
      }                                                                                         \
      psl = sl;                                                                                 \
      if (++sl == 3) { sl = 0; ph ^= 1; }
#pragma unroll 1
    for (int n = 0; n < 2; n++) { P1_STAGE() WG_WAIT(0); }
#pragma unroll 1
    for (int n = 2; n < 6; n++) {
      P1_STAGE()
      H_PAIR(h0, 32, SM_X + ((n - 2) >> 1) * 32768 + (n & 1) * 8192, B_PBE + ((n - 2) >> 1), n - 2)
    }
#pragma unroll 1
    for (int n = 6; n < 8; n++) { P1_STAGE() WG_WAIT(0); }
    WG_WAIT(0);
    reg_fence(a1);
    release(B_PBE + 3);
    uint32_t h1[24];
#pragma unroll
    for (int i = 0; i < 24; i++) h1[i] = pack_bf16(a1[2 * i], a1[2 * i + 1]);
    if (tid == 0) TS(3);
    float ab[64];
    const uint32_t plo = ((sbl + SM_X + wg * 2048) >> 4) | (1u << 16);
    const uint32_t wlo = ((sbl + SM_X + 16384) >> 4) | ((8192u >> 4) << 16);
#define PB_STEP()                                                                               \
    {                                                                                           \
      const uint32_t so = (m & 3) * 2048;                                                       \
      const uint32_t pa = (m == 8) ? plo + (SM_R >> 4) : plo + so;                              \
      mbar_wait(BAR(B_PBF + (m & 3)), (m >> 2) & 1);                                            \
      if (m < 2 || m == 8) {                                                                    \
        const uint32_t hb = B_HSF + (m == 8 ? 4 : 2 * m);                                       \
        mbar_wait(BAR(hb), 0); mbar_wait(BAR(hb + 1), 0);                                       \
      }                                                                                         \
      if (tid == 0) TS(100 + m);                                                                \
      WG_FENCE();                                                                               \
      wgmma_ss_n128(ab, dsc(pa, HI32), dsc(wlo + so, HI128), m != 0);                           \
      wgmma_ss_n128(ab, dsc(pa + 256, HI32), dsc(wlo + so + 128, HI128), 1);                    \
      WG_COMMIT();                                                                              \
      WG_WAIT(1);                                                                               \
      if (m > 0) release(B_PBE + ((m - 1) & 3));                                                \
      wgmma_ss_n128(ab, dsc(pa + 512, HI32), dsc(wlo + so + 256, HI128), 1);                    \
      wgmma_ss_n128(ab, dsc(pa + 768, HI32), dsc(wlo + so + 384, HI128), 1);                    \
      WG_COMMIT();                                                                              \
    }
#pragma unroll 1
    for (int m = 0; m < 3; m++) {
      PB_STEP()
      H_PAIR(h1, 24, SM_R + m * 8192, B_PBE + 3, 4 + m)
    }
#pragma unroll 1
    for (int m = 3; m < 16; m++) { PB_STEP() WG_WAIT(0); }
    WG_WAIT(0);
    reg_fence(ab);
    release(B_PBE + 3);
    if (tid == 0) TS(4);
    float ak[32];
    {
      mbar_wait(BAR(B_HSE + 2), 0);
#pragma unroll
      for (int u = 0; u < 4; u++) {
        uint32_t v[4];
#pragma unroll
        for (int w = 0; w < 4; w++)
          v[w] = jk ? pack_bf16(ab[8 * u + 2 * w], ab[8 * u + 2 * w + 1]) : pack_bf16(ab[32 + 8 * u + 2 * w], ab[33 + 8 * u + 2 * w]);
        *reinterpret_cast<uint4*>(smem + SM_R + u * 4096 + tid * 16) = make_uint4(v[0], v[1], v[2], v[3]);
      }
#pragma unroll
      for (int i = 0; i < 32; i++) ak[i] = jk ? ab[32 + i] : ab[i];
      fence_async_smem();
      __syncwarp();
      if (lane == 0) mbar_arrive(BAR(B_PS));
    }
#pragma unroll 1
    for (int m = 16; m < 20; m++) {
      const uint32_t so = (m & 3) * 2048;
      mbar_wait(BAR(B_PBF + (m & 3)), 0);
      if (tid == 0) TS(100 + m);
      WG_FENCE();
#pragma unroll
      for (int kk = 0; kk < 4; kk++) wgmma_ss_n64(ak, dsc(plo + so + kk * 256, HI32), dsc(wlo + so + kk * 128, HI128), 1);
      WG_COMMIT();
    }
    mbar_wait(BAR(B_PR), 0);
    {
      const uint4* pp = g_P + (size_t)cta_of(rb, j ^ 1) * 1024 + tid;
      uint4 p[4];
#pragma unroll
      for (int u = 0; u < 4; u++) p[u] = __ldcg(pp + u * 256);
      WG_WAIT(0);
      reg_fence(ak);
      if (tid == 0) TS(11 + 8);
      const uint32_t ost = sb + SM_R + 32768 + (warp * 16 + r16) * 128;
#define ADD2(x, y, w) pack_bf16((x) + __uint_as_float((w) << 16), (y) + __uint_as_float((w) & 0xffff0000u))
#pragma unroll
      for (int v = 0; v < 4; v++)
        stmatrix4(ost + (((2 * v + hf16) ^ (r16 & 7)) * 16), ADD2(ak[8 * v + 0], ak[8 * v + 1], p[v].x), ADD2(ak[8 * v + 2], ak[8 * v + 3], p[v].y),
                  ADD2(ak[8 * v + 4], ak[8 * v + 5], p[v].z), ADD2(ak[8 * v + 6], ak[8 * v + 7], p[v].w));
      __syncwarp();
      uint8_t* og = reinterpret_cast<uint8_t*>(out) + ((size_t)(rb * 128 + warp * 16 + (lane >> 3)) * 512 + jn * 128 + jk * 64) * 2 + (lane & 7) * 16;
#pragma unroll
      for (int v = 0; v < 4; v++) {
        const int r = v * 4 + (lane >> 3);
        *reinterpret_cast<uint4*>(og + v * 4096) =
            *reinterpret_cast<const uint4*>(smem + SM_R + 32768 + (warp * 16 + r) * 128 + (((lane & 7) ^ (r & 7)) * 16));
      }
    }
    if (tid == 0) TS(5);
  } else if (warp < 16) {
    const int tid = tid_now(), lane = tid & 31;
    const int at = tid - 256, a = (warp - 8) >> 2, w4 = warp & 3;
    const int g = lane >> 2, q = lane & 3;
    {
      reinterpret_cast<uint32_t*>(smem + SM_ONES)[at] = __ldg(reinterpret_cast<const uint32_t*>(gate_w) + at);
      asm volatile("bar.sync 1, 256;" ::: "memory");
      const int row = at >> 1, half = at & 1;
      float z0 = 0.f, z1 = 0.f;
#pragma unroll 1
      for (int cc = 0; cc < 4; cc++) {
        const int c = 2 * cc + half;
        mbar_wait(BAR(B_XFULL + 2 * cc), 0);
        mbar_wait(BAR(B_XFULL + 2 * cc + 1), 0);
#pragma unroll
        for (int u = 0; u < 8; u++) {
          const uint4 xv = *reinterpret_cast<const uint4*>(smem + SM_X + c * 16384 + row * 128 + ((u ^ (row & 7)) * 16));
          const uint4 gv = *reinterpret_cast<const uint4*>(smem + SM_ONES + c * 128 + u * 16);
          const uint32_t xs[4] = {xv.x, xv.y, xv.z, xv.w}, gs[4] = {gv.x, gv.y, gv.z, gv.w};
#pragma unroll
          for (int e = 0; e < 4; e++) {
            z0 = fmaf(__uint_as_float(xs[e] << 16), __uint_as_float(gs[e] << 16), z0);
            z1 = fmaf(__uint_as_float(xs[e] & 0xffff0000u), __uint_as_float(gs[e] & 0xffff0000u), z1);
          }
        }
      }
      z0 += z1;
      z0 += __shfl_xor_sync(0xffffffffu, z0, 1);
      asm volatile("bar.sync 1, 256;" ::: "memory");
      if (half == 0) reinterpret_cast<float*>(smem + SM_G)[row] = 1.0f / (1.0f + __expf(-z0));
      if (at < 128) reinterpret_cast<uint32_t*>(smem + SM_ONES)[at] = 0x3F803F80u;
      fence_async_smem();
      __syncwarp();
      if (lane == 0) mbar_arrive(BAR(B_GATE));
    }
    mbar_wait(BAR(B_GATE), 0);
    const int kb_min = (rb >= 2) ? 0 : (4 - 2 * rb);
    int Dv = 16 * w4 + g - 2 * q;
    const uint32_t fmask = (kb_min <= a) ? 0xffffffffu : 0u;
    const int kb_lo = max(a + 1, kb_min);
    const uint32_t sbl = sb & 0x3FFFFu;
    const uint32_t klo0 = ((sbl + SM_KV) >> 4) | (1u << 16);
    const uint32_t vlo0 = ((sbl + SM_KV + 4096) >> 4) | (((SM_ONES - SM_KV - 4096) >> 4) << 16);
#define KO(k) ((((k) >> 1) * 8192 + ((k) & 1) * 2048) >> 4)
    if (at == 0) TS(8);
    mbar_wait(BAR(B_QKV), 0);
    uint4 qf = ld_q(reinterpret_cast<const uint4*>(g_KVQ + (size_t)b * 49152 + 32768) + at);
#pragma unroll 1
    for (int hh = 0; hh < 4; hh++) {
      const uint32_t bo = (hh & 1) * (24576 >> 4);
      mbar_wait(BAR(B_KVF + (hh & 1)), hh >> 1);
      if (a < kb_min) {
        reinterpret_cast<uint4*>(smem + SM_KV + (hh & 1) * 24576 + 4096 + a * 2048)[tid_now() & 127] = make_uint4(0, 0, 0, 0);
        fence_async_smem();
        if (a == 0) asm volatile("bar.sync 6, 128;" ::: "memory"); else asm volatile("bar.sync 7, 128;" ::: "memory");
      }
      if (at == 0) TS(9 + 2 * hh);
      float O[12];
      uint32_t P[16];
      float mc0, mc1;
      const uint32_t od = bo + 1024 + a * 128, oo = bo + a * 128;
      asm volatile("" : "+r"(Dv));
      const int Dsel = (kb_min <= a) ? Dv : 1000;
      {
        float A[16], B[16];
        WG_FENCE();
        wgmma_rs_n32_set(A, qf.x, qf.y, qf.z, qf.w, dsc(klo0 + od, HI32));
        wgmma_rs_n32_set(B, qf.x, qf.y, qf.z, qf.w, dsc(klo0 + oo, HI32));
        WG_COMMIT();
        WG_WAIT(0);
        reg_fence(A); reg_fence(B);
        att_merged_half<0>(A, B, P, Dv, Dsel, fmask, mc0, mc1);
        WG_FENCE();
        wgmma_rs_n32_set(A, qf.x, qf.y, qf.z, qf.w, dsc(klo0 + od + 64, HI32));
        wgmma_rs_n32_set(B, qf.x, qf.y, qf.z, qf.w, dsc(klo0 + oo + 64, HI32));
        wgmma_rs_n24_set(O, P[0], P[1], P[2], P[3], vdsc(vlo0, od));
        wgmma_rs_n24_mnmaj(O, P[4], P[5], P[6], P[7], vdsc(vlo0, od + 32), 1);
        wgmma_rs_n24_mnmaj(O, P[8], P[9], P[10], P[11], vdsc(vlo0, oo), 1);
        wgmma_rs_n24_mnmaj(O, P[12], P[13], P[14], P[15], vdsc(vlo0, oo + 32), 1);
        WG_COMMIT();
        WG_WAIT(0);
        reg_fence(A); reg_fence(B); reg_fence_u(P);
        att_merged_half<1>(A, B, P, Dv, Dsel, fmask, mc0, mc1);
      }
      float S[32];
      WG_FENCE();
      att_s(S, qf, klo0 + bo + KO(a + 3));
      wgmma_rs_n24_mnmaj(O, P[0], P[1], P[2], P[3], vdsc(vlo0, od + 64), 1);
      wgmma_rs_n24_mnmaj(O, P[4], P[5], P[6], P[7], vdsc(vlo0, od + 96), 1);
      wgmma_rs_n24_mnmaj(O, P[8], P[9], P[10], P[11], vdsc(vlo0, oo + 64), 1);
      wgmma_rs_n24_mnmaj(O, P[12], P[13], P[14], P[15], vdsc(vlo0, oo + 96), 1);
      WG_COMMIT();
#pragma unroll 1
      for (int kb = a + 3; kb >= kb_lo; kb--) {
        const uint32_t oc = bo + KO(kb), on = bo + KO(max(kb - 1, a + 1));
        WG_WAIT(0);
        reg_fence(S); reg_fence_u(P);
        att_exp16(S, P, mc0, mc1);
        WG_FENCE();
        att_s(S, qf, klo0 + on);
          att_pv16(O, P, vlo0 + oc - (oc << 16), false);
        WG_COMMIT();
      }
      WG_WAIT(0);
      reg_fence(O); reg_fence(S);
      mbar_wait(BAR(B_QB), 0);
      const int t2 = tid_now(), l2 = t2 & 31;
      const uint4 qn = ld_q(reinterpret_cast<const uint4*>(g_KVQ + (size_t)b * 49152 + 32768) + (t2 - 256) + min(hh + 1, 3) * 256);
      if (FORCE_FALLBACK || !__all_sync(0xffffffffu, att_norm(O))) att_fallback(smem + SM_KV + (hh & 1) * 24576, qf, a, w4, kb_min, l2, O);
      const float* gs = reinterpret_cast<const float*>(smem + SM_G) + a * 64 + w4 * 16 + (l2 >> 2);
      const float g0 = gs[0], g1 = gs[8];
      if (a == 0) asm volatile("bar.sync 6, 128;" ::: "memory"); else asm volatile("bar.sync 7, 128;" ::: "memory");
      stmatrix4(sb + SM_KV + (hh & 1) * 24576 + a * 18432 + w4 * 512 + (l2 & 15) * 32 + (((l2 >> 4) ^ ((l2 >> 2) & 1)) * 16), pack_bf16(O[0] * g0, O[1] * g0), pack_bf16(O[2] * g1, O[3] * g1),
                pack_bf16(O[4] * g0, O[5] * g0), pack_bf16(O[6] * g1, O[7] * g1));
      fence_async_smem();
      __syncwarp();
      if (l2 == 0) mbar_arrive(BAR(B_OD + hh));
      if (at == 0) TS(10 + 2 * hh);
      qf = qn;
    }
    asm volatile("barrier.cluster.wait.aligned;" ::: "memory");
  } else {
    asm volatile("setmaxnreg.dec.sync.aligned.u32 32;");
    const int tid = tid_now(), lane = tid & 31;
    if (warp == 16) {
      if (sb & 1023) __trap();
      if (lane == 0) TS(50);
#pragma unroll 1
      for (int c = 0; c < 16; c++) {
        if (c + 2 < 8) {
          e_expect(BAR(B_XFULL + c + 2), 16384);
          e_tma2d(sb + SM_X + (c + 2) * 16384, &tm_x, BAR(B_XFULL + c + 2), (c + 2) * 64, rb * 128);
        }
        if (c == 0) { asm volatile("barrier.cluster.wait.aligned;" ::: "memory"); continue; }
        if (c >= 8) mbar_wait_t(BAR(B_WQE + (c & 3)), (c >> 2) & 1);
        e_expect(BAR(B_WQF + c), 12288);
        const uint32_t d = sb + SM_R + (c < 8 ? c : (c & 3)) * 12288;
        const int col = j * 64 + (c >> 3) * 32, kr = (c & 7) * 64;
        if ((c & 1) == cr) {
          e_tma2d_mc(d, &tm_wqkv, BAR(B_WQF + c), 512 + col, kr);
          e_tma2d_mc(d + 8192, &tm_wqkv, BAR(B_WQF + c), col, kr);
        } else {
          e_tma2d_mc(d + 4096, &tm_wqkv, BAR(B_WQF + c), 1024 + col, kr);
        }
        if (lane == 0 && c == 1) TS(52);
        if (c == 7) {
          if (lane == 0) { TS(53); prefetch_tmap(&tm_w1); prefetch_tmap(&tm_w2); prefetch_tmap(&tm_w2h); prefetch_tmap(&tm_wo); }
          __syncwarp();
        }
      }
      {
        int sl = 0; uint32_t ph = 0;
#pragma unroll 1
        for (int n = 0; n < 16; n++) {
          mbar_wait_t(BAR(B_W1E + sl), ph);
          e_expect(BAR(B_W1F + sl), 16384);
          e_tma2d_mc(sb + SM_R + sl * 16384 + cr * 8192, &tm_w1, BAR(B_W1F + sl), j * 224 + (n >> 3) * 128 + cr * 64, (n & 7) * 64);
          if (++sl == 3) { sl = 0; ph ^= 1; }
        }
      }
      if (lane == 0) TS(20);
      const int wc = jn * 128 + cr * 64;
#pragma unroll 1
      for (int m = 0; m < 20; m++) {
        const int st = m & 3;
        const uint32_t sw = sb + SM_X + st * 32768 + 16384, fb = BAR(B_PBF + st);
        const int ts = (m < 8) ? (m >> 1) : (m & 3), s = (j + 2 * ts) & 7;
        mbar_wait_t(BAR(B_PBE + st), (m >> 2) & 1);
        if (m < 12) {
          e_expect(fb, (m < 2 || m == 8) ? 16384u : 32768u);
          e_tma2d_mc(sw + cr * 8192, &tm_w2, fb, wc, 224 * s + (m < 8 ? (m & 1) * 64 : 128));
        } else if (m < 16) {
          e_expect(fb, 32768u);
          e_tma2d_mc(sw + cr * 8192, &tm_w2h, fb, wc, 224 * s + 192);
          e_tma2d_mc(sw + cr * 8192 + 4096, &tm_wo, fb, wc, 64 * s);
        } else {
          e_expect(fb, 24576u);
          e_tma2d_mc(sw + cr * 4096, &tm_wo, fb, jn * 128 + jk * 64, 64 * (2 * st + cr) + 32);
        }
        if (lane == 0) TS(60 + m);
      }
    } else {
      asm volatile("barrier.cluster.wait.aligned;" ::: "memory");
      if (tid == 544) {
        *(volatile uint32_t*)(smem + SM_EPOCH) = *(volatile uint32_t*)&g_flags[b * 32 + 0] + 1u;
        TS(54);
      }
      asm volatile("bar.sync 2, 96;" ::: "memory");
      const uint32_t epoch = *(volatile uint32_t*)(smem + SM_EPOCH);
      uint32_t* myf = &g_flags[b * 32];
      if (warp == 17) {
        mbar_wait_t(BAR(B_QKV), 0);
        if (lane == 0) TS(28);
        uint8_t* gkv = g_KVQ + (size_t)b * 49152;
        const int ns = min(rb, 2);
        auto load_kv = [&](int hh, int r0) {
          const uint32_t kb = sb + SM_KV + (hh & 1) * 24576 + 16384, fb = BAR(B_KVF + (hh & 1));
          e_expect(fb, (uint32_t)(ns + 1 - r0) * 8192u);
          for (int r = r0; r <= ns; r++) e_g2s(kb - r * 8192, g_KVQ + (size_t)cta_of(rb - r, j) * 49152 + hh * 8192, 8192, fb);
        };
        e_s2g(gkv, sb + SM_KV + 16384, 8192);
        e_s2g(gkv + 8192, sb + SM_KV + 24576 + 16384, 8192);
        bulk_commit();
        bulk_wait_all();
        e_st_flag(myf + 0, epoch);
        if (lane == 0) TS(30);
        if (lane >= 1 && lane <= ns) wait_flag(&g_flags[cta_of(rb - lane, j) * 32], epoch);
        __syncwarp();
        load_kv(0, 1);
        if (lane == 0) TS(31);
        mbar_wait_t(BAR(B_QB), 0);
        e_s2g(gkv + 16384, sb + SM_KV + 24576, 16384);
        bulk_commit();
        bulk_wait_read();
        load_kv(1, 1);
        bulk_wait_all();
        e_st_flag(myf + 6, epoch);
#pragma unroll 1
        for (int hh = 0; hh < 4; hh++) {
          mbar_wait_t(BAR(B_OD + hh), 0);
          e_s2g(g_A + ((size_t)b * 18 + 14 + hh) * 4096, sb + SM_KV + (hh & 1) * 24576, 2048);
          e_s2g(g_A + ((size_t)b * 18 + 14 + hh) * 4096 + 2048, sb + SM_KV + (hh & 1) * 24576 + 18432, 2048);
          bulk_commit();
          if (hh + 2 < 4) {
            if (hh == 0) { if (lane >= 1 && lane <= ns) wait_flag(&g_flags[cta_of(rb - lane, j) * 32 + 6], epoch); __syncwarp(); }
            bulk_wait_read();
            load_kv(hh + 2, 0);
          }
          if (hh & 1) {
            bulk_wait_all();
            e_st_flag(myf + 3 + (hh >> 1), epoch);
            if (lane == 0) TS(34 + (hh >> 1));
          }
        }
      } else if (warp == 18) {
        int s, fl;
        if (lane < 12) { s = (j + 2 * (lane & 3)) & 7; fl = 1 + (lane >> 2); }
        else if (lane < 20) { s = lane - 12; fl = 4; }
        else { s = j ^ 1; fl = 5; }
        const uint32_t* fp = &g_flags[cta_of(rb, s) * 32 + fl];
        bool rdy = lane > 20;
        uint32_t seen = 0;
        auto need = [&](uint32_t bits) {
          uint32_t spins = 0;
          while ((seen & bits) != bits) {
            if (!rdy) rdy = (int32_t)(ld_flag(fp) - epoch) >= 0;
            seen = __ballot_sync(0xffffffffu, rdy);
            if ((seen & bits) != bits) __nanosleep(32);
            if (++spins > 8 * SPIN_LIMIT) __trap();
          }
        };
        const uint8_t* abase = g_A + (size_t)cta_of(rb, 0) * (18 * 4096);
#pragma unroll 1
        for (int m = 2; m < 20; m++) {
          if (m == 8) continue;
          const int st = m & 3;
          const uint32_t sa = sb + SM_X + st * 32768, fb = BAR(B_PBF + st);
          mbar_wait_t(BAR(B_PBE + st), (m >> 2) & 1);
          if (m == 4 || m == 5) mbar_wait_t(BAR(B_HSE + m - 4), 0);
          if (m < 16) {
            const int ts = (m < 8) ? (m >> 1) : (m & 3), p = (m < 8) ? (m & 1) * 4 : (m < 12 ? 8 : 12);
            need((m < 8) ? (1u << ts) : (m < 12 ? (16u << ts) : (0x110u << ts)));
            e_g2s(sa, abase + (size_t)(((j + 2 * ts) & 7) * 36 + p) * 4096, 16384, fb);
          } else {
            need(0x1000u << (2 * st));
            e_g2s(sa, abase + (size_t)((2 * st) * 36 + 16) * 4096, 8192, fb);
            need(0x2000u << (2 * st));
            e_g2s(sa + 8192, abase + (size_t)((2 * st + 1) * 36 + 16) * 4096, 8192, fb);
          }
        }
        need(1u << 20);
        e_arrive(BAR(B_PR));
      } else {
        e_l2_prefetch(w1_raw + (size_t)b * 14336, 14336);
        mbar_wait_t(BAR(B_XFULL + 5), 0);
        e_l2_prefetch(w2_raw + (size_t)b * 14336, 14336);
        e_l2_prefetch(wo_raw + (size_t)b * 4096, 4096);
#pragma unroll 1
        for (int u = 0; u < 7; u++) {
          mbar_wait_t(BAR(B_HSF + u), 0);
          e_s2g(g_A + ((size_t)b * 18 + 2 * u) * 4096, sb + (u < 4 ? SM_X + (u >> 1) * 32768 + (u & 1) * 8192 : SM_R + (u - 4) * 8192), 8192);
          bulk_commit();
          if (u == 1) { bulk_wait_read(); e_arrive(BAR(B_HSE + 0)); }
          if (u == 3 || u == 6) {
            bulk_wait_all();
            e_st_flag(myf + (u == 3 ? 1 : 2), epoch);
            e_arrive(BAR(B_HSE + (u == 3 ? 1 : 2)));
            if (lane == 0) TS(u == 3 ? 32 : 33);
          }
        }
        mbar_wait_t(BAR(B_PS), 0);
        e_s2g(g_P + (size_t)b * 1024, sb + SM_R, 16384);
        bulk_commit();
        bulk_wait_all();
        e_st_flag(myf + 5, epoch);
        if (lane == 0) TS(36);
      }
    }
    __syncwarp();
  }
}

typedef CUresult (*EncFn)(CUtensorMap*, CUtensorMapDataType, cuuint32_t, void*, const cuuint64_t*, const cuuint64_t*,
                          const cuuint32_t*, const cuuint32_t*, CUtensorMapInterleave, CUtensorMapSwizzle,
                          CUtensorMapL2promotion, CUtensorMapFloatOOBfill);

static void enc2d(EncFn enc, CUtensorMap* tm, const void* p, uint64_t inner, uint64_t outer, uint32_t bi, uint32_t bo) {
  const CUtensorMapSwizzle swz = (bi == 32) ? CU_TENSOR_MAP_SWIZZLE_64B : CU_TENSOR_MAP_SWIZZLE_128B;
  cuuint64_t dims[2] = {inner, outer};
  cuuint64_t str[1] = {inner * 2};
  cuuint32_t box[2] = {bi, bo};
  cuuint32_t es[2] = {1, 1};
  enc(tm, CU_TENSOR_MAP_DATA_TYPE_BFLOAT16, 2, const_cast<void*>(p), dims, str, box, es, CU_TENSOR_MAP_INTERLEAVE_NONE,
      swz, CU_TENSOR_MAP_L2_PROMOTION_L2_256B, CU_TENSOR_MAP_FLOAT_OOB_FILL_NONE);
}

}

extern "C" void kernel_launch(void* const* d_in, const int* in_sizes, int n_in, void* d_out, int out_size) {
  using namespace gm;
  (void)in_sizes; (void)n_in; (void)out_size;
  static EncFn enc = nullptr;
  if (!enc) {
    void* fn = nullptr;
    cudaDriverEntryPointQueryResult qr;
    cudaGetDriverEntryPoint("cuTensorMapEncodeTiled", &fn, cudaEnableDefault, &qr);
    enc = (EncFn)fn;
    cudaFuncSetAttribute(fused_kernel, cudaFuncAttributeMaxDynamicSharedMemorySize, (int)SM_TOTAL);
  }
  const void* x = d_in[0];
  const void* wqkv = d_in[1];
  const void* wo = d_in[2];
  const void* w1 = d_in[4];
  const void* w2 = d_in[5];
  const __nv_bfloat16* gate_w = (const __nv_bfloat16*)d_in[6];
  CUtensorMap tm_x, tm_wqkv, tm_w1, tm_w2, tm_w2h, tm_wo;
  enc2d(enc, &tm_x, x, 512, 2048, 64, 128);
  enc2d(enc, &tm_wqkv, wqkv, 1536, 512, 32, 64);
  enc2d(enc, &tm_w1, w1, 1792, 512, 64, 64);
  enc2d(enc, &tm_w2, w2, 512, 1792, 64, 64);
  enc2d(enc, &tm_w2h, w2, 512, 1792, 64, 32);
  enc2d(enc, &tm_wo, wo, 512, 512, 64, 32);
  fused_kernel<<<128, NTHREADS, SM_TOTAL>>>(tm_x, tm_wqkv, tm_w1, tm_w2, tm_w2h, tm_wo, (__nv_bfloat16*)d_out, gate_w,
                                            (const uint8_t*)w1, (const uint8_t*)w2, (const uint8_t*)wo);
}
```
